```python
import torch

def _softmax(x, axis=-1):
    return torch.softmax(x, dim=axis)
def _gelu(x):
    return torch.nn.functional.gelu(x, approximate="tanh")
def _silu(x):
    return torch.nn.functional.silu(x)
def _sigmoid(x):
    return torch.sigmoid(x)
def _layernorm(x, axis=-1, eps=1e-5):
    m = x.mean(dim=axis, keepdim=True)
    v = x.var(dim=axis, keepdim=True, unbiased=False)
    return (x - m) / torch.sqrt(v + eps)
def _scatter_add(tgt, idx, src, axis=0):
    return tgt.clone().index_add_(axis, idx, src)
def _segment_sum(src, seg, n):
    out = torch.zeros((n,) + src.shape[1:], dtype=src.dtype)
    return out.index_add_(0, seg, src)
def _pad(x, pw):
    flat = tuple(v for pair in reversed(pw) for v in pair)
    return torch.nn.functional.pad(x, flat)

kernel_name = 'concat_heads__ssm_conv_h3__grouped_kv_mqa__prompt'

def setup_inputs():

    _w = (lambda a: (lambda t: t.to(torch.bfloat16) if t.is_floating_point() else t)(torch.as_tensor(a)))
    def _A_setup():
        B, S, D = 1, 2048, 512
        ks = 4
        return {
            "q": _w((lambda *s: torch.randn(*s, dtype=torch.bfloat16) * 0.05)(B, S, D)),
            "k": _w((lambda *s: torch.randn(*s, dtype=torch.bfloat16) * 0.2)(B, S, D)),
            "v": _w((lambda *s: torch.randn(*s, dtype=torch.bfloat16) * 0.2)(B, S, D)),
            "shift_k": _w((lambda *s: torch.randn(*s, dtype=torch.bfloat16) * 0.2)(D, ks) * 0.5),
            "ssm_k": _w((lambda *s: torch.randn(*s, dtype=torch.bfloat16) * 0.4)(D, S) * (1.0 / S ** 0.5)),
            "ssm_D": _w((lambda *s: torch.randn(*s, dtype=torch.bfloat16) * 0.2)(D)),
        }
    _A_in = _A_setup()

    def _B_setup():
        B, S, D, H = 1, 2048, 512, 32
        Dh = D // H
        return {
            "x": _w((lambda *s: torch.randn(*s, dtype=torch.bfloat16) * 0.05)(B, S, D)),
            "wq": _w((lambda *s: torch.randn(*s, dtype=torch.bfloat16) * 0.8)(D, H * Dh)),
            "wk": _w((lambda *s: torch.randn(*s, dtype=torch.bfloat16) * 0.8)(D, Dh)),
            "wv": _w((lambda *s: torch.randn(*s, dtype=torch.bfloat16) * 0.05)(D, Dh)),
            "wo": _w((lambda *s: torch.randn(*s, dtype=torch.bfloat16) * 0.05)(H * Dh, D)),
        }
    _B_in = _B_setup()

    return {
        "A_q": _A_in["q"],
        "A_k": _A_in["k"],
        "A_v": _A_in["v"],
        "A_shift_k": _A_in["shift_k"],
        "A_ssm_k": _A_in["ssm_k"],
        "A_ssm_D": _A_in["ssm_D"],
        "B_x": _B_in["x"],
        "B_wq": _B_in["wq"],
        "B_wk": _B_in["wk"],
        "B_wv": _B_in["wv"],
        "B_wo": _B_in["wo"],
    }

def reference(A_q, A_k, A_v, A_shift_k, A_ssm_k, A_ssm_D, B_x, B_wq, B_wk, B_wv, B_wo):
    def _A_ref(q, k, v, shift_k, ssm_k, ssm_D):
        B, S, D = q.shape
        ks = shift_k.shape[-1]
        k_pad = _pad(k, ((0, 0), (ks - 1, 0), (0, 0)))
        k_shift = torch.zeros_like(k)
        for t in range(ks):
            k_shift = k_shift + k_pad[:, t:t + S, :] * shift_k[:, ks - 1 - t][None, None, :]
        kv = k_shift * v
        L = 2 * S
        kv_pad = _pad(kv, ((0, 0), (0, S), (0, 0)))
        kf_pad = _pad(ssm_k, ((0, 0), (0, S)))
        kv_f = (lambda x, axes=(-2,-1): torch.fft.rfft2(x.float(), dim=axes))(kv_pad[:, None, :, :], axes=(1, 2))
        kf_f = (lambda x, axes=(-2,-1): torch.fft.rfft2(x.float(), dim=axes))(kf_pad[:, None, :], axes=(1, 2))
        kf_f = (lambda x, *d: x.permute(*d))(kf_f, 1, 2, 0)
        y_f = kv_f * kf_f[None, :, :, :]
        y = (lambda x, s, axes=(-2,-1): torch.fft.irfft2(x, s=s, dim=axes).to(torch.bfloat16))(y_f, (1, L), axes=(1, 2))[:, 0, :S, :]
        y = y + kv * ssm_D[None, None, :]
        return q * y

    def _B_ref(x, wq, wk, wv, wo):
        B, S, D = x.shape
        H = 32
        Dh = D // H
        q = (lambda x, *d: x.permute(*d))((x @ wq).reshape(B, S, H, Dh), 0, 2, 1, 3)
        k = x @ wk
        v = x @ wv
        scores = torch.einsum("bhqd,bkd->bhqk", q, k) * (Dh ** -0.5)
        p = _softmax(scores, axis=-1)
        o = torch.einsum("bhqk,bkd->bhqd", p, v)
        return (lambda x, *d: x.permute(*d))(o, 0, 2, 1, 3).reshape(B, S, H * Dh) @ wo

    a = _A_ref(A_q, A_k, A_v, A_shift_k, A_ssm_k, A_ssm_D)
    b = _B_ref(B_x, B_wq, B_wk, B_wv, B_wo)
    return torch.concatenate([a, b], axis=-1)
```

```cpp
#include <cuda_runtime.h>
#include <cuda_bf16.h>
#include <cuda.h>
#include <stdint.h>

typedef __nv_bfloat16 bf16;

__device__ __align__(1024) bf16 g_kv[4 * 2048 * 8];
__device__ __align__(16) float g_stat[4 * 32];
__device__ __align__(1024) bf16 g_o[2048 * 512];
__device__ __align__(1024) bf16 g_xp[512 * 2 * 128 * 8];
__device__ __align__(1024) bf16 g_z[512 * 2048];
__device__ unsigned int g_cnt3;
__device__ unsigned int g_cntA;
__device__ unsigned int g_cnt;
__device__ unsigned int g_cnt2[32];
__device__ unsigned int g_epoch;

constexpr uint32_t OFF_X    = 0;
constexpr uint32_t OFF_WQ   = 65536;
constexpr uint32_t OFF_K    = 0;
constexpr uint32_t OFF_V    = 65536;
constexpr uint32_t OFF_ONES = 131072;
constexpr uint32_t OFF_HT   = 163840;
constexpr uint32_t OFF_XP   = 197120;
constexpr uint32_t OFF_WKV  = 217600;
constexpr uint32_t OFF_WO01 = 65536;
constexpr uint32_t OFF_WO23 = 131072;
constexpr uint32_t OFF_O    = 0;
constexpr uint32_t OFF_MISC = 229376;
constexpr uint32_t SMEM_BYTES = OFF_MISC + 1024;
constexpr uint32_t DB = 1024;
constexpr uint32_t HT_STRIDE = 8320, HT_TB = 4160, XP_STRIDE = 5120, XP_PLANE = 2560, XP_PAD = 512;

enum { MB_WQ0 = 1, MB_KV = 5, MB_WO0 = 6, MB_O = 10, MB_XP = 11, MB_KV2 = 12, MB_COUNT = 13 };
constexpr uint32_t OFF_STAT = OFF_MISC + 128;

__device__ __forceinline__ uint32_t smem_u32(const void* p) { return (uint32_t)__cvta_generic_to_shared(p); }
__device__ __forceinline__ void mbar_init(uint32_t bar, uint32_t cnt) {
    asm volatile("mbarrier.init.shared::cta.b64 [%0], %1;" ::"r"(bar), "r"(cnt) : "memory");
}
__device__ __forceinline__ void mbar_expect_tx(uint32_t bar, uint32_t bytes) {
    asm volatile("mbarrier.arrive.expect_tx.shared::cta.b64 _, [%0], %1;" ::"r"(bar), "r"(bytes) : "memory");
}
__device__ __forceinline__ void mbar_wait(uint32_t bar, uint32_t parity) {
    uint32_t ok;
    uint32_t spins = 0;
    do {
        asm volatile("{\n.reg .pred p;\nmbarrier.try_wait.parity.shared::cta.b64 p, [%1], %2;\nselp.u32 %0, 1, 0, p;\n}\n"
                     : "=r"(ok) : "r"(bar), "r"(parity) : "memory");
    } while (!ok && ++spins < (1u << 22));
}
__device__ __forceinline__ void tma_2d(uint32_t dst, const CUtensorMap* tm, int c0, int c1, uint32_t bar) {
    asm volatile("cp.async.bulk.tensor.2d.shared::cluster.global.mbarrier::complete_tx::bytes [%0], [%1, {%3, %4}], [%2];"
                 ::"r"(dst), "l"(tm), "r"(bar), "r"(c0), "r"(c1) : "memory");
}
__device__ __forceinline__ void bulk_g2s(uint32_t dst, const void* src, uint32_t bytes, uint32_t bar) {
    asm volatile("cp.async.bulk.shared::cluster.global.mbarrier::complete_tx::bytes [%0], [%1], %2, [%3];"
                 ::"r"(dst), "l"(src), "r"(bytes), "r"(bar) : "memory");
}
__device__ __forceinline__ void tma_3d(uint32_t dst, const CUtensorMap* tm, int c0, int c1, int c2, uint32_t bar) {
    asm volatile("cp.async.bulk.tensor.3d.shared::cluster.global.mbarrier::complete_tx::bytes [%0], [%1, {%3, %4, %5}], [%2];"
                 ::"r"(dst), "l"(tm), "r"(bar), "r"(c0), "r"(c1), "r"(c2) : "memory");
}
__device__ __forceinline__ void tma_2d_mc(uint32_t dst, const CUtensorMap* tm, int c0, int c1, uint32_t bar) {
    asm volatile("cp.async.bulk.tensor.2d.shared::cluster.global.mbarrier::complete_tx::bytes.multicast::cluster [%0], [%1, {%3, %4}], [%2], %5;"
                 ::"r"(dst), "l"(tm), "r"(bar), "r"(c0), "r"(c1), "h"((unsigned short)3) : "memory");
}
__device__ __forceinline__ void bulk_g2s_mc(uint32_t dst, const void* src, uint32_t bytes, uint32_t bar) {
    asm volatile("cp.async.bulk.shared::cluster.global.mbarrier::complete_tx::bytes.multicast::cluster [%0], [%1], %2, [%3], %4;"
                 ::"r"(dst), "l"(src), "r"(bytes), "r"(bar), "h"((unsigned short)3) : "memory");
}
__device__ __forceinline__ void cluster_arrive() { asm volatile("barrier.cluster.arrive.release.aligned;" ::: "memory"); }
__device__ __forceinline__ void cluster_arrive_relaxed() { asm volatile("barrier.cluster.arrive.relaxed.aligned;" ::: "memory"); }
__device__ __forceinline__ void cluster_wait() { asm volatile("barrier.cluster.wait.acquire.aligned;" ::: "memory"); }
__device__ __forceinline__ void fence_proxy_async() { asm volatile("fence.proxy.async.shared::cta;" ::: "memory"); }
__device__ __forceinline__ void fence_proxy_async_global() { asm volatile("fence.proxy.async.global;" ::: "memory"); }
__device__ __forceinline__ void bar_arrive(int id, int nthreads) { asm volatile("bar.arrive %0, %1;" ::"r"(id), "r"(nthreads) : "memory"); }
__device__ __forceinline__ uint4 lds128(uint32_t a) {
    uint4 v; asm volatile("ld.shared.v4.b32 {%0,%1,%2,%3}, [%4];" : "=r"(v.x), "=r"(v.y), "=r"(v.z), "=r"(v.w) : "r"(a)); return v;
}
__device__ __forceinline__ void wg_fence() { asm volatile("wgmma.fence.sync.aligned;" ::: "memory"); }
__device__ __forceinline__ void wg_commit() { asm volatile("wgmma.commit_group.sync.aligned;" ::: "memory"); }
template <int N> __device__ __forceinline__ void wg_wait() { asm volatile("wgmma.wait_group.sync.aligned %0;" ::"n"(N) : "memory"); }
__device__ __forceinline__ void named_bar(int id, int nthreads) { asm volatile("bar.sync %0, %1;" ::"r"(id), "r"(nthreads) : "memory"); }
__device__ __forceinline__ uint32_t prmt(uint32_t a, uint32_t b, uint32_t sel) {
    uint32_t d; asm("prmt.b32 %0, %1, %2, %3;" : "=r"(d) : "r"(a), "r"(b), "r"(sel)); return d;
}
__device__ __forceinline__ uint32_t pack_bf16(float lo, float hi) {
    uint32_t r; asm("cvt.rn.bf16x2.f32 %0, %1, %2;" : "=r"(r) : "f"(hi), "f"(lo)); return r;
}
__device__ __forceinline__ uint32_t hmul2_rn(uint32_t a, uint32_t b) {
    uint32_t d; asm("mul.rn.bf16x2 %0, %1, %2;" : "=r"(d) : "r"(a), "r"(b)); return d;
}
__device__ __forceinline__ uint32_t hadd2_rn(uint32_t a, uint32_t b) {
    uint32_t d; asm("add.rn.bf16x2 %0, %1, %2;" : "=r"(d) : "r"(a), "r"(b)); return d;
}
__device__ __forceinline__ float bf_lo(uint32_t v) { return __uint_as_float(v << 16); }
__device__ __forceinline__ float bf_hi(uint32_t v) { return __uint_as_float(v & 0xFFFF0000u); }
__device__ __forceinline__ uint32_t lds32(uint32_t a) { uint32_t v; asm volatile("ld.shared.b32 %0, [%1];" : "=r"(v) : "r"(a)); return v; }
__device__ __forceinline__ uint2 lds64(uint32_t a) { uint2 v; asm volatile("ld.shared.v2.b32 {%0,%1}, [%2];" : "=r"(v.x), "=r"(v.y) : "r"(a)); return v; }
__device__ __forceinline__ float4 lds128f(uint32_t a) {
    float4 v; asm volatile("ld.shared.v4.f32 {%0,%1,%2,%3}, [%4];" : "=f"(v.x), "=f"(v.y), "=f"(v.z), "=f"(v.w) : "r"(a)); return v;
}
__device__ __forceinline__ void sts64(uint32_t a, uint32_t x, uint32_t y) { asm volatile("st.shared.v2.b32 [%0], {%1,%2};" ::"r"(a), "r"(x), "r"(y) : "memory"); }
__device__ __forceinline__ void sts128(uint32_t a, uint32_t x, uint32_t y, uint32_t z, uint32_t w) {
    asm volatile("st.shared.v4.b32 [%0], {%1,%2,%3,%4};" ::"r"(a), "r"(x), "r"(y), "r"(z), "r"(w) : "memory");
}
__device__ __forceinline__ void sts128f(uint32_t a, float x, float y, float z, float w) {
    asm volatile("st.shared.v4.f32 [%0], {%1,%2,%3,%4};" ::"r"(a), "f"(x), "f"(y), "f"(z), "f"(w) : "memory");
}
__device__ __forceinline__ void stsm_x4_trans(uint32_t a, uint32_t r0, uint32_t r1, uint32_t r2, uint32_t r3) {
    asm volatile("stmatrix.sync.aligned.m8n8.x4.trans.shared.b16 [%0], {%1,%2,%3,%4};" ::"r"(a), "r"(r0), "r"(r1), "r"(r2), "r"(r3) : "memory");
}
__device__ __forceinline__ unsigned ld_acquire(const unsigned* p) {
    unsigned v; asm volatile("ld.acquire.gpu.global.u32 %0, [%1];" : "=r"(v) : "l"(p) : "memory"); return v;
}
__device__ __forceinline__ void red_release_add(unsigned* p, unsigned v) {
    asm volatile("red.release.gpu.global.add.u32 [%0], %1;" ::"l"(p), "r"(v) : "memory");
}
__device__ __forceinline__ void spin_until(const unsigned* p, unsigned target) {
    unsigned spins = 0;
    while ((int)(ld_acquire(p) - target) < 0) {
        __nanosleep(20);
        if (++spins > (1u << 22)) __trap();
    }
}

__device__ __forceinline__ void wg_ss_n8_tb(float* d, uint32_t alo, uint32_t ahi, uint32_t blo, uint32_t bhi, int scale_d) {
    asm volatile("{\n.reg .pred p;\n.reg .b64 da, db;\nmov.b64 da, {%4, %5};\nmov.b64 db, {%6, %7};\nsetp.ne.b32 p, %8, 0;\n"
    "wgmma.mma_async.sync.aligned.m64n8k16.f32.bf16.bf16 {%0, %1, %2, %3}, da, db, p, 1, 1, 0, 1;\n}\n"
    : "+f"(d[0]), "+f"(d[1]), "+f"(d[2]), "+f"(d[3])
    : "r"(alo), "r"(ahi), "r"(blo), "r"(bhi), "r"(scale_d));
}
__device__ __forceinline__ void wg_ss_n32_tb(float* d, uint32_t alo, uint32_t ahi, uint32_t blo, uint32_t bhi, int scale_d) {
    asm volatile("{\n.reg .pred p;\n.reg .b64 da, db;\nmov.b64 da, {%16, %17};\nmov.b64 db, {%18, %19};\nsetp.ne.b32 p, %20, 0;\n"
    "wgmma.mma_async.sync.aligned.m64n32k16.f32.bf16.bf16 {%0, %1, %2, %3, %4, %5, %6, %7, %8, %9, %10, %11, %12, %13, %14, %15}, da, db, p, 1, 1, 0, 1;\n}\n"
    : "+f"(d[0]), "+f"(d[1]), "+f"(d[2]), "+f"(d[3]), "+f"(d[4]), "+f"(d[5]), "+f"(d[6]), "+f"(d[7]), "+f"(d[8]), "+f"(d[9]), "+f"(d[10]), "+f"(d[11]), "+f"(d[12]), "+f"(d[13]), "+f"(d[14]), "+f"(d[15])
    : "r"(alo), "r"(ahi), "r"(blo), "r"(bhi), "r"(scale_d));
}
__device__ __forceinline__ void wg_ss_n64_tb(float* d, uint32_t alo, uint32_t ahi, uint32_t blo, uint32_t bhi, int scale_d) {
    asm volatile("{\n.reg .pred p;\n.reg .b64 da, db;\nmov.b64 da, {%32, %33};\nmov.b64 db, {%34, %35};\nsetp.ne.b32 p, %36, 0;\n"
    "wgmma.mma_async.sync.aligned.m64n64k16.f32.bf16.bf16 {%0, %1, %2, %3, %4, %5, %6, %7, %8, %9, %10, %11, %12, %13, %14, %15, %16, %17, %18, %19, %20, %21, %22, %23, %24, %25, %26, %27, %28, %29, %30, %31}, da, db, p, 1, 1, 0, 1;\n}\n"
    : "+f"(d[0]), "+f"(d[1]), "+f"(d[2]), "+f"(d[3]), "+f"(d[4]), "+f"(d[5]), "+f"(d[6]), "+f"(d[7]), "+f"(d[8]), "+f"(d[9]), "+f"(d[10]), "+f"(d[11]), "+f"(d[12]), "+f"(d[13]), "+f"(d[14]), "+f"(d[15]), "+f"(d[16]), "+f"(d[17]), "+f"(d[18]), "+f"(d[19]), "+f"(d[20]), "+f"(d[21]), "+f"(d[22]), "+f"(d[23]), "+f"(d[24]), "+f"(d[25]), "+f"(d[26]), "+f"(d[27]), "+f"(d[28]), "+f"(d[29]), "+f"(d[30]), "+f"(d[31])
    : "r"(alo), "r"(ahi), "r"(blo), "r"(bhi), "r"(scale_d));
}
__device__ __forceinline__ void wg_qk64(float* d, uint32_t a0, uint32_t a1, uint32_t a2, uint32_t a3, uint32_t dlo, uint32_t dhi) {
    asm volatile("{\n.reg .pred p;\n.reg .b64 dsc;\nmov.b64 dsc, {%36, %37};\nsetp.ne.b32 p, 0, 0;\n"
    "wgmma.mma_async.sync.aligned.m64n64k16.f32.bf16.bf16 {%0, %1, %2, %3, %4, %5, %6, %7, %8, %9, %10, %11, %12, %13, %14, %15, %16, %17, %18, %19, %20, %21, %22, %23, %24, %25, %26, %27, %28, %29, %30, %31}, {%32, %33, %34, %35}, dsc, p, 1, 1, 0;\n}\n"
    : "=f"(d[0]), "=f"(d[1]), "=f"(d[2]), "=f"(d[3]), "=f"(d[4]), "=f"(d[5]), "=f"(d[6]), "=f"(d[7]), "=f"(d[8]), "=f"(d[9]), "=f"(d[10]), "=f"(d[11]), "=f"(d[12]), "=f"(d[13]), "=f"(d[14]), "=f"(d[15]), "=f"(d[16]), "=f"(d[17]), "=f"(d[18]), "=f"(d[19]), "=f"(d[20]), "=f"(d[21]), "=f"(d[22]), "=f"(d[23]), "=f"(d[24]), "=f"(d[25]), "=f"(d[26]), "=f"(d[27]), "=f"(d[28]), "=f"(d[29]), "=f"(d[30]), "=f"(d[31])
    : "r"(a0), "r"(a1), "r"(a2), "r"(a3), "r"(dlo), "r"(dhi));
}
__device__ __forceinline__ void wg_pv24(float* d, uint32_t a0, uint32_t a1, uint32_t a2, uint32_t a3, uint32_t dlo, uint32_t dhi, int scale_d) {
    asm volatile("{\n.reg .pred p;\n.reg .b64 dsc;\nmov.b64 dsc, {%16, %17};\nsetp.ne.b32 p, %18, 0;\n"
    "wgmma.mma_async.sync.aligned.m64n24k16.f32.bf16.bf16 {%0, %1, %2, %3, %4, %5, %6, %7, %8, %9, %10, %11}, {%12, %13, %14, %15}, dsc, p, 1, 1, 1;\n}\n"
    : "+f"(d[0]), "+f"(d[1]), "+f"(d[2]), "+f"(d[3]), "+f"(d[4]), "+f"(d[5]), "+f"(d[6]), "+f"(d[7]), "+f"(d[8]), "+f"(d[9]), "+f"(d[10]), "+f"(d[11])
    : "r"(a0), "r"(a1), "r"(a2), "r"(a3), "r"(dlo), "r"(dhi), "r"(scale_d));
}
__device__ __forceinline__ void wg_conv32(float* d, uint32_t a0, uint32_t a1, uint32_t a2, uint32_t a3, uint32_t dlo, uint32_t dhi, int scale_d) {
    asm volatile("{\n.reg .pred p;\n.reg .b64 dsc;\nmov.b64 dsc, {%20, %21};\nsetp.ne.b32 p, %22, 0;\n"
    "wgmma.mma_async.sync.aligned.m64n32k16.f32.bf16.bf16 {%0, %1, %2, %3, %4, %5, %6, %7, %8, %9, %10, %11, %12, %13, %14, %15}, {%16, %17, %18, %19}, dsc, p, 1, 1, 0;\n}\n"
    : "+f"(d[0]), "+f"(d[1]), "+f"(d[2]), "+f"(d[3]), "+f"(d[4]), "+f"(d[5]), "+f"(d[6]), "+f"(d[7]), "+f"(d[8]), "+f"(d[9]), "+f"(d[10]), "+f"(d[11]), "+f"(d[12]), "+f"(d[13]), "+f"(d[14]), "+f"(d[15])
    : "r"(a0), "r"(a1), "r"(a2), "r"(a3), "r"(dlo), "r"(dhi), "r"(scale_d));
}
__device__ __forceinline__ void wg_qk64d(float* d, uint32_t a0, uint32_t a1, uint32_t a2, uint32_t a3, uint64_t dsc) {
    asm volatile("{\n.reg .pred p;\nsetp.ne.b32 p, 0, 0;\n"
    "wgmma.mma_async.sync.aligned.m64n64k16.f32.bf16.bf16 {%0, %1, %2, %3, %4, %5, %6, %7, %8, %9, %10, %11, %12, %13, %14, %15, %16, %17, %18, %19, %20, %21, %22, %23, %24, %25, %26, %27, %28, %29, %30, %31}, {%32, %33, %34, %35}, %36, p, 1, 1, 0;\n}\n"
    : "=f"(d[0]), "=f"(d[1]), "=f"(d[2]), "=f"(d[3]), "=f"(d[4]), "=f"(d[5]), "=f"(d[6]), "=f"(d[7]), "=f"(d[8]), "=f"(d[9]), "=f"(d[10]), "=f"(d[11]), "=f"(d[12]), "=f"(d[13]), "=f"(d[14]), "=f"(d[15]), "=f"(d[16]), "=f"(d[17]), "=f"(d[18]), "=f"(d[19]), "=f"(d[20]), "=f"(d[21]), "=f"(d[22]), "=f"(d[23]), "=f"(d[24]), "=f"(d[25]), "=f"(d[26]), "=f"(d[27]), "=f"(d[28]), "=f"(d[29]), "=f"(d[30]), "=f"(d[31])
    : "r"(a0), "r"(a1), "r"(a2), "r"(a3), "l"(dsc));
}
__device__ __forceinline__ void wg_pv24d(float* d, uint32_t a0, uint32_t a1, uint32_t a2, uint32_t a3, uint64_t dsc, int scale_d) {
    asm volatile("{\n.reg .pred p;\nsetp.ne.b32 p, %17, 0;\n"
    "wgmma.mma_async.sync.aligned.m64n24k16.f32.bf16.bf16 {%0, %1, %2, %3, %4, %5, %6, %7, %8, %9, %10, %11}, {%12, %13, %14, %15}, %16, p, 1, 1, 1;\n}\n"
    : "+f"(d[0]), "+f"(d[1]), "+f"(d[2]), "+f"(d[3]), "+f"(d[4]), "+f"(d[5]), "+f"(d[6]), "+f"(d[7]), "+f"(d[8]), "+f"(d[9]), "+f"(d[10]), "+f"(d[11])
    : "r"(a0), "r"(a1), "r"(a2), "r"(a3), "l"(dsc), "r"(scale_d));
}
__device__ __forceinline__ void wg_pv24d1(float* d, uint32_t a0, uint32_t a1, uint32_t a2, uint32_t a3, uint64_t dsc) {
    asm volatile("{\n.reg .pred p;\nsetp.eq.b32 p, 0, 0;\n"
    "wgmma.mma_async.sync.aligned.m64n24k16.f32.bf16.bf16 {%0, %1, %2, %3, %4, %5, %6, %7, %8, %9, %10, %11}, {%12, %13, %14, %15}, %16, p, 1, 1, 1;\n}\n"
    : "+f"(d[0]), "+f"(d[1]), "+f"(d[2]), "+f"(d[3]), "+f"(d[4]), "+f"(d[5]), "+f"(d[6]), "+f"(d[7]), "+f"(d[8]), "+f"(d[9]), "+f"(d[10]), "+f"(d[11])
    : "r"(a0), "r"(a1), "r"(a2), "r"(a3), "l"(dsc));
}

__device__ __forceinline__ float ex2f(float a) { float e; asm("ex2.approx.ftz.f32 %0, %1;" : "=f"(e) : "f"(a)); return e; }
__device__ __forceinline__ uint32_t exp_mufu_pair(float a, float b) { return pack_bf16(ex2f(a), ex2f(b)); }
__device__ __forceinline__ uint32_t exp_poly_pair(float a, float b, uint32_t C1, float TWO, uint32_t ONE2) {
    float ra, rb; uint32_t u, m, t, p, y;
    asm("fma.rn.f32 %0, %1, %2, 766.0078125;" : "=f"(ra) : "f"(a), "f"(TWO));
    asm("fma.rn.f32 %0, %1, %2, 766.0078125;" : "=f"(rb) : "f"(b), "f"(TWO));
    asm("prmt.b32 %0, %1, %2, 0x6521;" : "=r"(u) : "r"(__float_as_uint(ra)), "r"(__float_as_uint(rb)));
    asm("lop3.b32 %0, %1, 0x007F007F, %2, 0xEA;" : "=r"(m) : "r"(u), "r"(ONE2));
    asm("{.reg .b32 k; mov.b32 k, 0x3EAF3EAF; fma.rn.bf16x2 %0, %1, k, %2;}" : "=r"(t) : "r"(m), "r"(C1));
    asm("{.reg .b32 k; mov.b32 k, 0x3F323F32; fma.rn.bf16x2 %0, %1, %2, k;}" : "=r"(p) : "r"(t), "r"(m));
    asm("{.reg .b32 tt; sub.u32 tt, %1, %2; add.u32 %0, tt, %3;}" : "=r"(y) : "r"(u), "r"(m), "r"(p));
    return y;
}
#define PMASK 0x03FF

struct Params {
    const bf16 *A_q, *A_k, *A_v, *shift_k, *ssm_k, *ssm_D, *wk, *wv, *x, *wq;
    bf16* out;
    uint32_t c1, one2; float two;
};

__global__ void __cluster_dims__(2, 1, 1) __launch_bounds__(512, 1)
fused_kernel(const __grid_constant__ CUtensorMap tm_x, const __grid_constant__ CUtensorMap tm_wq,
             const __grid_constant__ CUtensorMap tm_wo, const __grid_constant__ CUtensorMap tm_o,
             const __grid_constant__ CUtensorMap tm_xp, const Params P) {
    extern __shared__ __align__(1024) uint8_t smem[];
    const uint32_t sb = smem_u32(smem);
    const int tid = threadIdx.x, lane = tid & 31;
    const int warp = __shfl_sync(0xffffffffu, tid >> 5, 0), wg = warp >> 2, wl = warp & 3;
    const int g = lane >> 2, t = lane & 3;
    const int c = blockIdx.x, r = c >> 5, qb = c & 31, rank = c & 1;
    const uint32_t mb = sb + OFF_MISC;
    float* s_stat = reinterpret_cast<float*>(smem + OFF_STAT);

    unsigned epoch = 0;
    if (tid == 0) {
        if ((sb & 0xFFFFFFu) != DB) __trap();
        for (int i = 0; i < MB_COUNT; i++) mbar_init(mb + 8 * i, 1);
        asm volatile("fence.mbarrier_init.release.cluster;" ::: "memory");
        fence_proxy_async();
    }
    if (lane == 0 && wg == 1) {
        const CUtensorMap* tm = (wl == 0) ? &tm_wq : (wl == 1) ? &tm_wo : (wl == 2) ? &tm_o : &tm_xp;
        asm volatile("prefetch.tensormap [%0];" ::"l"(tm) : "memory");
    }
    {
        const int row0 = warp * 4;
#pragma unroll
        for (int i = 0; i < 8; i++) {
            const int row = row0 + (i >> 1), ck = (i & 1) * 32 + lane;
            const uint32_t dst = sb + OFF_X + (ck >> 3) * 8192 + row * 128 + (((ck & 7) ^ (row & 7)) << 4);
            asm volatile("cp.async.cg.shared.global [%0], [%1], 16;" ::"r"(dst), "l"(P.x + (size_t)(qb * 64 + row) * 512 + ck * 8) : "memory");
        }
        asm volatile("cp.async.commit_group;" ::: "memory");
    }
    cluster_arrive_relaxed();
    if (tid == 0 || tid == 128 || tid == 384) epoch = *reinterpret_cast<volatile unsigned*>(&g_epoch);

    const uint4 wkv = *reinterpret_cast<const uint4*>((r < 2 ? P.wk : P.wv) + tid * 16 + (r & 1) * 8);
    cluster_wait();
    if (tid == 128) {
        for (int ch = 0; ch < 4; ch++) {
            mbar_expect_tx(mb + 8 * (MB_WQ0 + ch), 32768);
            for (int w = 2 * rank; w < 2 * rank + 2; w++)
                tma_2d_mc(sb + OFF_WQ + ch * 32768 + w * 8192, &tm_wq, r * 128 + w * 32, ch * 128, mb + 8 * (MB_WQ0 + ch));
        }
    }
    sts128(sb + OFF_WKV + tid * 16, wkv.x, wkv.y, wkv.z, wkv.w);
    if (tid < 256) {
        sts128(sb + OFF_XP + (tid >> 5) * XP_PLANE + (tid & 31) * 16, 0u, 0u, 0u, 0u);
    }
    asm volatile("cp.async.wait_all;" ::: "memory");
    fence_proxy_async();
    __syncthreads();
    const int cp = tid >> 1, half = tid & 1, R0 = 16 * c + 8 * half;
    const uint32_t xa_hi = (1024 >> 4) | (1u << 30);
    if (wg == 0) {
        float d[4];
        wg_fence();
#pragma unroll
        for (int k = 0; k < 32; k++) {
            const uint32_t alo = ((DB + OFF_X + (k >> 2) * 8192 + (k & 3) * 32) >> 4) | (1u << 16);
            const uint32_t blo = ((DB + OFF_WKV + k * 256) >> 4) | ((128 >> 4) << 16);
            wg_ss_n8_tb(d, alo, xa_hi, blo, 8, k > 0);
        }
        wg_commit();
        wg_wait<0>();
        const uint32_t p0 = pack_bf16(d[0], d[1]), p1 = pack_bf16(d[2], d[3]);
        const int key = qb * 64 + wl * 16 + g;
        uint32_t* dst = reinterpret_cast<uint32_t*>(g_kv + (size_t)r * 16384);
        dst[key * 4 + t] = p0;
        dst[(key + 8) * 4 + t] = p1;
        float st;
        if (r < 2) {
            float n0 = bf_lo(p0) * bf_lo(p0) + bf_hi(p0) * bf_hi(p0), n1 = bf_lo(p1) * bf_lo(p1) + bf_hi(p1) * bf_hi(p1);
            n0 += __shfl_xor_sync(~0u, n0, 1); n1 += __shfl_xor_sync(~0u, n1, 1);
            n0 += __shfl_xor_sync(~0u, n0, 2); n1 += __shfl_xor_sync(~0u, n1, 2);
            st = (n0 != n0 || n1 != n1) ? __int_as_float(0x7f800000) : fmaxf(n0, n1);
        } else {
            const float a0 = fabsf(bf_lo(p0)), a1 = fabsf(bf_hi(p0)), a2 = fabsf(bf_lo(p1)), a3 = fabsf(bf_hi(p1));
            st = fmaxf(fmaxf(a0, a1), fmaxf(a2, a3));
            if (a0 != a0 || a1 != a1 || a2 != a2 || a3 != a3) st = __int_as_float(0x7f800000);
        }
        const unsigned stb = __reduce_max_sync(~0u, __float_as_uint(st));
        reinterpret_cast<volatile unsigned*>(s_stat)[24 + wl] = stb;
        named_bar(7, 128);
        if (tid == 0) {
            const volatile unsigned* sm = reinterpret_cast<volatile unsigned*>(s_stat) + 24;
            const unsigned m = max(max(sm[0], sm[1]), max(sm[2], sm[3]));
            g_stat[r * 32 + qb] = __uint_as_float(m);
            red_release_add(&g_cnt, 1u);
        }
    }
    uint32_t kk[11], vv[8];
    uint4 sw;
    const int tau = tid & 127;
    uint4 hc[2]; uint32_t hx[2];
    uint32_t qa[4], qb4[4];
    {
        float d[16];
        const uint32_t b_hi = (512 >> 4) | (2u << 30);
#pragma unroll 1
        for (int ch = 0; ch < 2; ch++) {
            mbar_wait(mb + 8 * (MB_WQ0 + ch), 0);
            wg_fence();
#pragma unroll
            for (int kk8 = 0; kk8 < 8; kk8++) {
                const int k = ch * 8 + kk8;
                const uint32_t alo = ((DB + OFF_X + (k >> 2) * 8192 + (k & 3) * 32) >> 4) | (1u << 16);
                const uint32_t blo = ((DB + OFF_WQ + ch * 32768 + wg * 8192 + kk8 * 1024) >> 4) | (1u << 16);
                wg_ss_n32_tb(d, alo, xa_hi, blo, b_hi, k > 0);
            }
            wg_commit();
        }
    {
        const uint32_t* kp = reinterpret_cast<const uint32_t*>(P.A_k) + cp;
        const uint32_t* vp = reinterpret_cast<const uint32_t*>(P.A_v) + cp;
#pragma unroll
        for (int i = 0; i < 11; i++) {
            const int s = R0 - 3 + i;
            kk[i] = (s >= 0) ? __ldg(kp + (size_t)s * 256) : 0u;
        }
#pragma unroll
        for (int i = 0; i < 8; i++) vv[i] = __ldg(vp + (size_t)(R0 + i) * 256);
    }
    sw = *reinterpret_cast<const uint4*>(P.shift_k + 8 * cp);

    {
        const bf16* hrow = P.ssm_k + (size_t)(4 * c + wg) * 2048;
#pragma unroll
        for (int i = 0; i < 2; i++) {
            const int q = tau + 128 * i;
            hc[i] = *reinterpret_cast<const uint4*>(hrow + 8 * q);
            hx[i] = (q < 255) ? (uint32_t)*reinterpret_cast<const unsigned short*>(hrow + 8 * q + 8) : 0u;
        }
    }
#pragma unroll 1
        for (int ch = 2; ch < 4; ch++) {
            mbar_wait(mb + 8 * (MB_WQ0 + ch), 0);
            wg_fence();
#pragma unroll
            for (int kk8 = 0; kk8 < 8; kk8++) {
                const int k = ch * 8 + kk8;
                const uint32_t alo = ((DB + OFF_X + (k >> 2) * 8192 + (k & 3) * 32) >> 4) | (1u << 16);
                const uint32_t blo = ((DB + OFF_WQ + ch * 32768 + wg * 8192 + kk8 * 1024) >> 4) | (1u << 16);
                wg_ss_n32_tb(d, alo, xa_hi, blo, b_hi, k > 0);
            }
            wg_commit();
        }
        wg_wait<0>();
        const float qs = 0.25f * 1.4426950408889634f;
        qa[0] = pack_bf16(d[0] * qs, d[1] * qs);   qa[1] = pack_bf16(d[2] * qs, d[3] * qs);
        qa[2] = pack_bf16(d[4] * qs, d[5] * qs);   qa[3] = pack_bf16(d[6] * qs, d[7] * qs);
        qb4[0] = pack_bf16(d[8] * qs, d[9] * qs);  qb4[1] = pack_bf16(d[10] * qs, d[11] * qs);
        qb4[2] = pack_bf16(d[12] * qs, d[13] * qs); qb4[3] = pack_bf16(d[14] * qs, d[15] * qs);
        auto n2 = [](uint32_t a, uint32_t b) { return bf_lo(a) * bf_lo(a) + bf_hi(a) * bf_hi(a) + bf_lo(b) * bf_lo(b) + bf_hi(b) * bf_hi(b); };
        float n0 = n2(qa[0], qa[2]), n1 = n2(qa[1], qa[3]), n2a = n2(qb4[0], qb4[2]), n3 = n2(qb4[1], qb4[3]);
#pragma unroll
        for (int o = 1; o < 4; o <<= 1) {
            n0 += __shfl_xor_sync(~0u, n0, o); n1 += __shfl_xor_sync(~0u, n1, o);
            n2a += __shfl_xor_sync(~0u, n2a, o); n3 += __shfl_xor_sync(~0u, n3, o);
        }
        float st = fmaxf(fmaxf(n0, n1), fmaxf(n2a, n3));
        if (n0 != n0 || n1 != n1 || n2a != n2a || n3 != n3) st = __int_as_float(0x7f800000);
#pragma unroll
        for (int o = 4; o < 32; o <<= 1) st = fmaxf(st, __shfl_xor_sync(~0u, st, o));
        if (lane == 0) s_stat[4 + warp] = st;
    }
    if (tid == 384) spin_until(&g_cnt, (epoch + 1u) * 128u);
    __syncthreads();
    cluster_arrive_relaxed();
    if (warp == 12) {
        cluster_wait();
        if (lane == 0) {
            fence_proxy_async_global();
            mbar_expect_tx(mb + 8 * MB_KV, 65536);
            mbar_expect_tx(mb + 8 * MB_KV2, 65536);
            for (int h = 0; h < 2; h++)
                for (int pl = 2 * rank; pl < 2 * rank + 2; pl++)
                    bulk_g2s_mc(sb + OFF_K + pl * 32768 + h * 16384, reinterpret_cast<const uint8_t*>(g_kv) + pl * 32768 + h * 16384, 16384,
                                mb + 8 * (h ? MB_KV2 : MB_KV));
            if (c == 0) *reinterpret_cast<volatile unsigned*>(&g_epoch) = epoch + 1u;
        }
        __syncwarp();
        asm volatile("cp.async.cg.shared.global [%0], [%1], 16;" ::"r"(sb + OFF_STAT + 128 + lane * 16), "l"(&g_stat[lane * 4]) : "memory");
    }
    {
        const uint32_t W0 = prmt(sw.x, sw.z, 0x5410), W1 = prmt(sw.x, sw.z, 0x7632);
        const uint32_t W2 = prmt(sw.y, sw.w, 0x5410), W3 = prmt(sw.y, sw.w, 0x7632);
        uint32_t a[8];
#pragma unroll
        for (int u = 0; u < 8; u++) {
            uint32_t x = hmul2_rn(kk[u], W3);
            x = hadd2_rn(x, hmul2_rn(kk[u + 1], W2));
            x = hadd2_rn(x, hmul2_rn(kk[u + 2], W1));
            x = hadd2_rn(x, hmul2_rn(kk[u + 3], W0));
            a[u] = hmul2_rn(x, vv[u]);
        }
        uint4* dst = reinterpret_cast<uint4*>(g_xp) + ((size_t)(2 * cp) * 128 + c) * 2 + half;
        dst[0] = make_uint4(prmt(a[0], a[1], 0x5410), prmt(a[2], a[3], 0x5410), prmt(a[4], a[5], 0x5410), prmt(a[6], a[7], 0x5410));
        dst[256] = make_uint4(prmt(a[0], a[1], 0x7632), prmt(a[2], a[3], 0x7632), prmt(a[4], a[5], 0x7632), prmt(a[6], a[7], 0x7632));
    }
#pragma unroll
    for (int i = 0; i < 4; i++)
        sts128(sb + OFF_ONES + (i * 512 + tid) * 16, 0x3F803F80u, 0x3F803F80u, 0x3F803F80u, 0x3F803F80u);
    const uint32_t ht = sb + OFF_HT + wg * HT_STRIDE;
    {
#pragma unroll
        for (int i = 0; i < 2; i++) {
            const int q = tau + 128 * i;
            const uint4 w = hc[i];
            sts128(ht + (256 - q) * 16, prmt(w.w, 0, 0x1032), prmt(w.z, 0, 0x1032), prmt(w.y, 0, 0x1032), prmt(w.x, 0, 0x1032));
            sts128(ht + HT_TB + (256 - q) * 16, prmt(hx[i], w.w, 0x7610), prmt(w.w, w.z, 0x7610), prmt(w.z, w.y, 0x7610), prmt(w.y, w.x, 0x7610));
        }
        if (tau < 3) sts128(ht + (257 + tau) * 16, 0u, 0u, 0u, 0u);
        else if (tau < 5) sts128(ht + HT_TB + (255 + tau) * 16, 0u, 0u, 0u, 0u);
        if (tau == 0) sts128(ht + HT_TB + 257 * 16, hc[0].x & 0xFFFFu, 0u, 0u, 0u);
    }
    if (warp == 12) {
        asm volatile("cp.async.wait_all;" ::: "memory");
        const float4 v = lds128f(sb + OFF_STAT + 128 + lane * 16);
        float m = fmaxf(fmaxf(v.x, v.y), fmaxf(v.z, v.w));
        m = fmaxf(m, __shfl_xor_sync(~0u, m, 1)); m = fmaxf(m, __shfl_xor_sync(~0u, m, 2)); m = fmaxf(m, __shfl_xor_sync(~0u, m, 4));
        const float k0 = __shfl_sync(~0u, m, 0), k1 = __shfl_sync(~0u, m, 8), v0 = __shfl_sync(~0u, m, 16), v1 = __shfl_sync(~0u, m, 24);
        if (lane == 0) { s_stat[0] = k0 + k1; s_stat[1] = fmaxf(v0, v1); }
    }
    fence_proxy_async();
    __syncthreads();

    if (tid == 256) red_release_add(&g_cntA, 1u);
    __syncwarp();
    mbar_wait(mb + 8 * MB_KV, 0);
    bool fast;
    {
        const float qn = fmaxf(fmaxf(s_stat[4 + 4 * wg], s_stat[5 + 4 * wg]), fmaxf(s_stat[6 + 4 * wg], s_stat[7 + 4 * wg]));
        const float kn = s_stat[0], vm = s_stat[1];
        fast = (qn * kn <= 4096.f) && (vm <= 1073741824.f) && (vm >= 9.313225746154785e-10f || vm == 0.f);
        fast = __all_sync(0xffffffffu, fast) != 0;
    }
    const uint32_t klo0 = ((DB + OFF_K) >> 4) | ((32768u >> 4) << 16), khi = 128 >> 4;
    const uint32_t vlo0 = ((DB + OFF_V) >> 4) | ((128u >> 4) << 16), vhi = 32768u >> 4;
    float o[12];
#pragma unroll
    for (int i = 0; i < 12; i++) o[i] = 0.f;
#pragma unroll 1
    for (int hh = 0; hh < 2; hh++) {
        if (hh == 1 && tid == 384) {
            spin_until(&g_cntA, (epoch + 1u) * 128u);
            fence_proxy_async_global();
            mbar_expect_tx(mb + 8 * MB_XP, 16384);
            for (int i = 0; i < 8; i++)
                tma_3d(sb + OFF_XP + (i >> 1) * XP_STRIDE + (i & 1) * XP_PLANE + XP_PAD, &tm_xp, 0, i & 1, (4 * c + (i >> 1)) * 128, mb + 8 * MB_XP);
        }
        __syncwarp();
        const uint32_t q0 = hh ? qb4[0] : qa[0], q1 = hh ? qb4[1] : qa[1], q2 = hh ? qb4[2] : qa[2], q3 = hh ? qb4[3] : qa[3];
        float s[32];
        uint32_t p[16];
        if (fast) {
            const uint32_t C1 = P.c1, ONE2 = P.one2; const float TWO = P.two;
            uint64_t dk = ((uint64_t)khi << 32) | klo0, dv = ((uint64_t)vhi << 32) | vlo0;
#pragma unroll
            for (int i = 0; i < 12; i++) asm volatile("mov.b32 %0, 0;" : "=f"(o[i]));
            wg_fence();
            wg_qk64d(s, q0, q1, q2, q3, dk);
            wg_commit();
#pragma unroll 1
            for (int seg = 0; seg < 2; seg++) {
                const uint32_t vend = vlo0 + (seg ? 2048u : 15u * 64u);
#pragma unroll 1
            do {
                wg_wait<0>();
#pragma unroll
                for (int i = 0; i < 16; i++) {
                    const bool poly = (PMASK >> i) & 1;
                    p[i] = poly ? exp_poly_pair(s[2 * i], s[2 * i + 1], C1, TWO, ONE2) : exp_mufu_pair(s[2 * i], s[2 * i + 1]);
                }
                asm("add.u64 %0, %0, 64;" : "+l"(dk));
                wg_fence();
                wg_pv24d1(o, p[0], p[1], p[2], p[3], dv);
                wg_pv24d1(o, p[4], p[5], p[6], p[7], dv + 16);
                wg_pv24d1(o, p[8], p[9], p[10], p[11], dv + 32);
                wg_pv24d1(o, p[12], p[13], p[14], p[15], dv + 48);
                wg_qk64d(s, q0, q1, q2, q3, dk);
                wg_commit();
                asm("add.u64 %0, %0, 64;" : "+l"(dv));
            } while ((uint32_t)dv != vend);
                if (seg == 0) mbar_wait(mb + 8 * MB_KV2, 0);
            }
            wg_wait<0>();
        } else {
            mbar_wait(mb + 8 * MB_KV2, 0);
            float m0 = -INFINITY, m1 = -INFINITY;
#pragma unroll 1
            for (int kb = 0; kb < 32; kb++) {
                wg_fence();
                wg_qk64(s, q0, q1, q2, q3, klo0 + kb * 64, khi);
                wg_commit();
                wg_wait<0>();
#pragma unroll
                for (int J = 0; J < 8; J++) {
                    m0 = fmaxf(m0, fmaxf(s[4 * J], s[4 * J + 1]));
                    m1 = fmaxf(m1, fmaxf(s[4 * J + 2], s[4 * J + 3]));
                }
            }
            m0 = fmaxf(m0, __shfl_xor_sync(~0u, m0, 1)); m1 = fmaxf(m1, __shfl_xor_sync(~0u, m1, 1));
            m0 = fmaxf(m0, __shfl_xor_sync(~0u, m0, 2)); m1 = fmaxf(m1, __shfl_xor_sync(~0u, m1, 2));
#pragma unroll 1
            for (int kb = 0; kb < 32; kb++) {
                wg_fence();
                wg_qk64(s, q0, q1, q2, q3, klo0 + kb * 64, khi);
                wg_commit();
                wg_wait<0>();
#pragma unroll
                for (int J = 0; J < 8; J++) {
                    p[2 * J] = exp_mufu_pair(s[4 * J] - m0, s[4 * J + 1] - m0);
                    p[2 * J + 1] = exp_mufu_pair(s[4 * J + 2] - m1, s[4 * J + 3] - m1);
                }
                wg_fence();
                wg_pv24(o, p[0], p[1], p[2], p[3], vlo0 + kb * 64, vhi, kb > 0);
                wg_pv24(o, p[4], p[5], p[6], p[7], vlo0 + kb * 64 + 16, vhi, 1);
                wg_pv24(o, p[8], p[9], p[10], p[11], vlo0 + kb * 64 + 32, vhi, 1);
                wg_pv24(o, p[12], p[13], p[14], p[15], vlo0 + kb * 64 + 48, vhi, 1);
                wg_commit();
                wg_wait<0>();
            }
        }
        const float i0 = 1.0f / o[8], i1 = 1.0f / o[10];
        {
            const uint32_t a0 = pack_bf16(o[0] * i0, o[1] * i0), a1 = pack_bf16(o[4] * i0, o[5] * i0);
            const uint32_t b0 = pack_bf16(o[2] * i1, o[3] * i1), b1 = pack_bf16(o[6] * i1, o[7] * i1);
            const bool odd = t & 1;
            const uint32_t xa = __shfl_xor_sync(~0u, odd ? a0 : a1, 1), xb = __shfl_xor_sync(~0u, odd ? b0 : b1, 1);
            uint2* dst = reinterpret_cast<uint2*>(g_o + (size_t)(qb * 64 + wl * 16 + g) * 512 + (8 * r + 2 * wg + hh) * 16 + (odd ? 8 + 2 * (t - 1) : 2 * t));
            dst[0] = odd ? make_uint2(xa, a1) : make_uint2(a0, xa);
            dst[8 * 128] = odd ? make_uint2(xb, b1) : make_uint2(b0, xb);
        }
    }

    __syncthreads();
    if (tid == 0) {
        red_release_add(&g_cnt2[qb], 1u);
        for (int ch = 0; ch < 2; ch++) {
            mbar_expect_tx(mb + 8 * (MB_WO0 + ch), 32768);
            for (int w = 0; w < 2; w++) tma_2d(sb + OFF_WO01 + ch * 32768 + w * 16384, &tm_wo, r * 128 + w * 64, ch * 128, mb + 8 * (MB_WO0 + ch));
        }
    }
    mbar_wait(mb + 8 * MB_XP, 0);
    {
        float d[64];
        const int wlog = (wl + wg) & 3;
        const uint32_t ta = ht + ((g & 1) ? 0u : HT_TB) + 4u * (1028 - 64 * wlog - ((g + 1) >> 1) + t);
        const uint32_t xlo = ((DB + OFF_XP + wg * XP_STRIDE + XP_PAD) >> 4) | ((XP_PLANE >> 4) << 16);
        const uint32_t xhi = 128 >> 4;
#define CONV_GROUP(E)                                                                                 \
        {                                                                                             \
            uint32_t a = ta - 32u * 32u * E, xb = xlo;                                                \
            _Pragma("unroll 1") for (int hf = 0; hf < 4; hf++) {                                      \
                uint32_t af[2][4];                                                                    \
                af[0][0] = lds32(a); af[0][1] = lds32(a - 16); af[0][2] = lds32(a + 16); af[0][3] = lds32(a); \
                af[1][0] = lds32(a - 32); af[1][1] = lds32(a - 48); af[1][2] = lds32(a - 16); af[1][3] = lds32(a - 32); \
                wg_fence();                                                                           \
                _Pragma("unroll") for (int J = E; J < 4; J++)                                         \
                    wg_conv32(d + 16 * J, af[0][0], af[0][1], af[0][2], af[0][3], xb + 32 * (J - E), xhi, (E > 0) ? 1 : hf); \
                _Pragma("unroll") for (int J = E; J < 4; J++)                                         \
                    wg_conv32(d + 16 * J, af[1][0], af[1][1], af[1][2], af[1][3], xb + 32 * (J - E) - 1, xhi, 1); \
                wg_commit();                                                                          \
                wg_wait<0>();                                                                         \
                a -= 64; xb -= 2;                                                                     \
            }                                                                                         \
        }
        CONV_GROUP(0)
        CONV_GROUP(1)
        if (tid == 384) {
            spin_until(&g_cnt2[qb], (epoch + 1u) * 4u);
            fence_proxy_async_global();
            mbar_expect_tx(mb + 8 * MB_O, 65536);
            for (int kb = 0; kb < 8; kb++) tma_2d(sb + OFF_O + kb * 8192, &tm_o, kb * 64, qb * 64, mb + 8 * MB_O);
        }
        __syncwarp();
        CONV_GROUP(2)
        CONV_GROUP(3)
#undef CONV_GROUP
        const uint32_t bufA = ht + lane * 16, bufB = sb + OFF_ONES + wg * 8192 + lane * 16;
        named_bar(2 + wg, 128);
        if (wlog == 3) {
#pragma unroll
            for (int J = 0; J < 13; J++) sts128f(bufA + J * 512, d[4 * J], d[4 * J + 1], d[4 * J + 2], d[4 * J + 3]);
        } else if (wlog == 1) {
#pragma unroll
            for (int J = 0; J < 15; J++) sts128f(bufB + J * 512, d[4 * J], d[4 * J + 1], d[4 * J + 2], d[4 * J + 3]);
        }
        named_bar(2 + wg, 128);
        if (wlog == 2) {
#pragma unroll
            for (int J = 1; J < 14; J++) {
                const float4 v = lds128f(bufA + (J - 1) * 512);
                d[4 * J] += v.x; d[4 * J + 1] += v.y; d[4 * J + 2] += v.z; d[4 * J + 3] += v.w;
            }
        } else if (wlog == 0) {
#pragma unroll
            for (int J = 1; J < 16; J++) {
                const float4 v = lds128f(bufB + (J - 1) * 512);
                d[4 * J] += v.x; d[4 * J + 1] += v.y; d[4 * J + 2] += v.z; d[4 * J + 3] += v.w;
            }
        }
        named_bar(2 + wg, 128);
        if (wlog == 2) {
#pragma unroll
            for (int J = 0; J < 14; J++) sts128f(bufA + J * 512, d[4 * J], d[4 * J + 1], d[4 * J + 2], d[4 * J + 3]);
        }
        named_bar(2 + wg, 128);
        if (wlog == 0) {
#pragma unroll
            for (int J = 2; J < 16; J++) {
                const float4 v = lds128f(bufA + (J - 2) * 512);
                d[4 * J] += v.x; d[4 * J + 1] += v.y; d[4 * J + 2] += v.z; d[4 * J + 3] += v.w;
            }
            __syncwarp();
            const uint32_t ya = ht + (16 * (8 * (lane >> 4) + (lane & 7)) + 8 * ((lane >> 3) & 1)) * 2;
#pragma unroll
            for (int J = 0; J < 16; J += 2) {
                stsm_x4_trans(ya + J * 256, pack_bf16(d[4 * J], d[4 * J + 1]), pack_bf16(d[4 * J + 2], d[4 * J + 3]),
                              pack_bf16(d[4 * J + 4], d[4 * J + 5]), pack_bf16(d[4 * J + 6], d[4 * J + 7]));
            }
        }
    }
    {
        named_bar(2 + wg, 128);
        const uint32_t dw = (uint32_t)*reinterpret_cast<const unsigned short*>(P.ssm_D + 4 * c + wg);
        const uint32_t d2 = dw | (dw << 16);
        const uint4 y0 = lds128(ht + tau * 16), y1 = lds128(ht + 2048 + tau * 16);
        const uint32_t xo = sb + OFF_XP + wg * XP_STRIDE + (tau & 1) * XP_PLANE + XP_PAD + (tau >> 1) * 16;
        const uint4 k0 = lds128(xo), k1 = lds128(xo + 1024);
        uint4* dst = reinterpret_cast<uint4*>(g_z + (size_t)(4 * c + wg) * 2048) + tau;
        dst[0] = make_uint4(hadd2_rn(y0.x, hmul2_rn(k0.x, d2)), hadd2_rn(y0.y, hmul2_rn(k0.y, d2)),
                            hadd2_rn(y0.z, hmul2_rn(k0.z, d2)), hadd2_rn(y0.w, hmul2_rn(k0.w, d2)));
        dst[128] = make_uint4(hadd2_rn(y1.x, hmul2_rn(k1.x, d2)), hadd2_rn(y1.y, hmul2_rn(k1.y, d2)),
                              hadd2_rn(y1.z, hmul2_rn(k1.z, d2)), hadd2_rn(y1.w, hmul2_rn(k1.w, d2)));
    }
    fence_proxy_async();
    __syncthreads();
    if (wg < 2) {
        if (tid == 0) {
            for (int ch = 2; ch < 4; ch++) {
                mbar_expect_tx(mb + 8 * (MB_WO0 + ch), 32768);
                for (int w = 0; w < 2; w++) tma_2d(sb + OFF_WO23 + (ch - 2) * 32768 + w * 16384, &tm_wo, r * 128 + w * 64, ch * 128, mb + 8 * (MB_WO0 + ch));
            }
        }
        __syncwarp();
        float d[32];
        mbar_wait(mb + 8 * MB_O, 0);
#pragma unroll 1
        for (int ch = 0; ch < 4; ch++) {
            mbar_wait(mb + 8 * (MB_WO0 + ch), 0);
            const uint32_t wbase = OFF_WO01 + ch * 32768;
            wg_fence();
#pragma unroll
            for (int kk8 = 0; kk8 < 8; kk8++) {
                const int k = ch * 8 + kk8;
                const uint32_t alo = ((DB + OFF_O + (k >> 2) * 8192 + (k & 3) * 32) >> 4) | (1u << 16);
                const uint32_t blo = ((DB + wbase + wg * 16384 + kk8 * 2048) >> 4) | (1u << 16);
                wg_ss_n64_tb(d, alo, xa_hi, blo, xa_hi, k > 0);
            }
            wg_commit();
        }
        wg_wait<0>();
        const bool odd = t & 1;
        bf16* orow = P.out + (size_t)(qb * 64 + wl * 16 + g) * 1024 + 512 + r * 128 + wg * 64 + (odd ? 8 + 2 * (t - 1) : 2 * t);
#pragma unroll
        for (int J = 0; J < 8; J += 2) {
            const uint32_t a0 = pack_bf16(d[4 * J], d[4 * J + 1]), a1 = pack_bf16(d[4 * J + 4], d[4 * J + 5]);
            const uint32_t b0 = pack_bf16(d[4 * J + 2], d[4 * J + 3]), b1 = pack_bf16(d[4 * J + 6], d[4 * J + 7]);
            const uint32_t xa = __shfl_xor_sync(~0u, odd ? a0 : a1, 1), xb = __shfl_xor_sync(~0u, odd ? b0 : b1, 1);
            *reinterpret_cast<uint2*>(orow + 8 * J) = odd ? make_uint2(xa, a1) : make_uint2(a0, xa);
            *reinterpret_cast<uint2*>(orow + 8 * 1024 + 8 * J) = odd ? make_uint2(xb, b1) : make_uint2(b0, xb);
        }
    } else {
        if (tid == 384) red_release_add(&g_cnt3, 1u);
        const int t2 = tid - 256;
        uint32_t qq[2][8];
#pragma unroll
        for (int it = 0; it < 2; it++) {
            const int cp2 = (t2 + 256 * it) >> 1, R2 = 16 * c + 8 * (t2 & 1);
            const uint32_t* qp = reinterpret_cast<const uint32_t*>(P.A_q) + cp2;
#pragma unroll
            for (int i = 0; i < 8; i++) qq[it][i] = __ldg(qp + (size_t)(R2 + i) * 256);
        }
        if (tid == 384) spin_until(&g_cnt3, (epoch + 1u) * 128u);
        named_bar(8, 256);
        uint4 z0[2], z1[2];
#pragma unroll
        for (int it = 0; it < 2; it++) {
            const int cp2 = (t2 + 256 * it) >> 1, R2 = 16 * c + 8 * (t2 & 1);
            z0[it] = __ldcg(reinterpret_cast<const uint4*>(g_z + (size_t)(2 * cp2) * 2048 + R2));
            z1[it] = __ldcg(reinterpret_cast<const uint4*>(g_z + (size_t)(2 * cp2 + 1) * 2048 + R2));
        }
#pragma unroll
        for (int it = 0; it < 2; it++) {
            const int cp2 = (t2 + 256 * it) >> 1, R2 = 16 * c + 8 * (t2 & 1);
            uint32_t* op = reinterpret_cast<uint32_t*>(P.out) + cp2;
            op[(size_t)(R2 + 0) * 512] = hmul2_rn(qq[it][0], prmt(z0[it].x, z1[it].x, 0x5410));
            op[(size_t)(R2 + 1) * 512] = hmul2_rn(qq[it][1], prmt(z0[it].x, z1[it].x, 0x7632));
            op[(size_t)(R2 + 2) * 512] = hmul2_rn(qq[it][2], prmt(z0[it].y, z1[it].y, 0x5410));
            op[(size_t)(R2 + 3) * 512] = hmul2_rn(qq[it][3], prmt(z0[it].y, z1[it].y, 0x7632));
            op[(size_t)(R2 + 4) * 512] = hmul2_rn(qq[it][4], prmt(z0[it].z, z1[it].z, 0x5410));
            op[(size_t)(R2 + 5) * 512] = hmul2_rn(qq[it][5], prmt(z0[it].z, z1[it].z, 0x7632));
            op[(size_t)(R2 + 6) * 512] = hmul2_rn(qq[it][6], prmt(z0[it].w, z1[it].w, 0x5410));
            op[(size_t)(R2 + 7) * 512] = hmul2_rn(qq[it][7], prmt(z0[it].w, z1[it].w, 0x7632));
        }
    }
}

typedef CUresult (*EncodeTiledFn)(CUtensorMap*, CUtensorMapDataType, cuuint32_t, void*, const cuuint64_t*, const cuuint64_t*,
                                  const cuuint32_t*, const cuuint32_t*, CUtensorMapInterleave, CUtensorMapSwizzle,
                                  CUtensorMapL2promotion, CUtensorMapFloatOOBfill);

static void make_map(EncodeTiledFn fn, CUtensorMap* m, const void* ptr, uint64_t cols, uint64_t rows, uint32_t bc, uint32_t br,
                     CUtensorMapSwizzle sw) {
    cuuint64_t dims[2] = {cols, rows};
    cuuint64_t strides[1] = {cols * 2};
    cuuint32_t box[2] = {bc, br};
    cuuint32_t es[2] = {1, 1};
    fn(m, CU_TENSOR_MAP_DATA_TYPE_BFLOAT16, 2, const_cast<void*>(ptr), dims, strides, box, es, CU_TENSOR_MAP_INTERLEAVE_NONE, sw,
       CU_TENSOR_MAP_L2_PROMOTION_L2_256B, CU_TENSOR_MAP_FLOAT_OOB_FILL_NONE);
}

extern "C" void kernel_launch(void* const* d_in, const int* in_sizes, int n_in, void* d_out, int out_size) {
    static EncodeTiledFn enc = nullptr;
    static void* g_o_ptr = nullptr;
    static void* g_xp_ptr = nullptr;
    if (!enc) {
        void* fn = nullptr;
        cudaDriverEntryPointQueryResult qr;
        cudaGetDriverEntryPoint("cuTensorMapEncodeTiled", &fn, cudaEnableDefault, &qr);
        enc = (EncodeTiledFn)fn;
        cudaGetSymbolAddress(&g_o_ptr, g_o);
        cudaGetSymbolAddress(&g_xp_ptr, g_xp);
        cudaFuncSetAttribute(fused_kernel, cudaFuncAttributeMaxDynamicSharedMemorySize, SMEM_BYTES);
    }
    Params P;
    P.A_q = (const bf16*)d_in[0]; P.A_k = (const bf16*)d_in[1]; P.A_v = (const bf16*)d_in[2];
    P.shift_k = (const bf16*)d_in[3]; P.ssm_k = (const bf16*)d_in[4]; P.ssm_D = (const bf16*)d_in[5];
    const void* x = d_in[6]; const void* wq = d_in[7];
    P.x = (const bf16*)x; P.wq = (const bf16*)wq;
    P.wk = (const bf16*)d_in[8]; P.wv = (const bf16*)d_in[9];
    const void* wo = d_in[10];
    P.out = (bf16*)d_out;
    P.c1 = 0xBD09BD09u; P.one2 = 0x3F803F80u; P.two = 2.0f;
    CUtensorMap tm_x, tm_wq, tm_wo, tm_o, tm_xp;
    {
        cuuint64_t dims[3] = {8, 2, 512 * 128};
        cuuint64_t strides[2] = {16, 32};
        cuuint32_t box[3] = {8, 1, 128};
        cuuint32_t es[3] = {1, 1, 1};
        enc(&tm_xp, CU_TENSOR_MAP_DATA_TYPE_BFLOAT16, 3, g_xp_ptr, dims, strides, box, es, CU_TENSOR_MAP_INTERLEAVE_NONE,
            CU_TENSOR_MAP_SWIZZLE_NONE, CU_TENSOR_MAP_L2_PROMOTION_NONE, CU_TENSOR_MAP_FLOAT_OOB_FILL_NONE);
    }
    make_map(enc, &tm_x, x, 512, 2048, 64, 64, CU_TENSOR_MAP_SWIZZLE_128B);
    make_map(enc, &tm_o, g_o_ptr, 512, 2048, 64, 64, CU_TENSOR_MAP_SWIZZLE_128B);
    make_map(enc, &tm_wq, wq, 512, 512, 32, 128, CU_TENSOR_MAP_SWIZZLE_64B);
    make_map(enc, &tm_wo, wo, 512, 512, 64, 128, CU_TENSOR_MAP_SWIZZLE_128B);
    fused_kernel<<<128, 512, SMEM_BYTES>>>(tm_x, tm_wq, tm_wo, tm_o, tm_xp, P);
}
```
